```python
import torch

def _softmax(x, axis=-1):
    return torch.softmax(x, dim=axis)
def _gelu(x):
    return torch.nn.functional.gelu(x, approximate="tanh")
def _silu(x):
    return torch.nn.functional.silu(x)
def _sigmoid(x):
    return torch.sigmoid(x)
def _layernorm(x, axis=-1, eps=1e-5):
    m = x.mean(dim=axis, keepdim=True)
    v = x.var(dim=axis, keepdim=True, unbiased=False)
    return (x - m) / torch.sqrt(v + eps)
def _scatter_add(tgt, idx, src, axis=0):
    return tgt.clone().index_add_(axis, idx, src)
def _segment_sum(src, seg, n):
    out = torch.zeros((n,) + src.shape[1:], dtype=src.dtype)
    return out.index_add_(0, seg, src)
def _pad(x, pw):
    flat = tuple(v for pair in reversed(pw) for v in pair)
    return torch.nn.functional.pad(x, flat)

kernel_name = 'recurrent_scan__spectral_fnet__mixer_channel_mlp__prompt'

def setup_inputs():

    _w = (lambda a: (lambda t: t.to(torch.bfloat16) if t.is_floating_point() else t)(torch.as_tensor(a)))
    def _A_setup():
        B, S, D = 1, 2048, 512
        ns = torch.arange(S)[:, None] * torch.arange(S)[None, :]
        nd = torch.arange(D)[:, None] * torch.arange(D)[None, :]
        Ws_re = torch.cos(-2.0 * torch.pi * ns / S).to(float)
        Ws_im = torch.sin(-2.0 * torch.pi * ns / S).to(float)
        Wd_re = torch.cos(-2.0 * torch.pi * nd / D).to(float)
        Wd_im = torch.sin(-2.0 * torch.pi * nd / D).to(float)
        return {
            "x": _w((lambda *s: torch.randn(*s, dtype=torch.bfloat16) * 0.05)(B, S, D)),
            "dft_seq_re": _w(Ws_re),
            "dft_seq_im": _w(Ws_im),
            "dft_hid_re": _w(Wd_re),
            "dft_hid_im": _w(Wd_im),
        }
    _A_in = _A_setup()

    def _B_setup():
        B, S, D, F = 1, 2048, 512, 1792
        return {
            "x": _w((lambda *s: torch.randn(*s, dtype=torch.bfloat16) * 0.05)(B, S, D)),
            "w1": _w((lambda *s: torch.randn(*s, dtype=torch.bfloat16) * 0.8)(D, F) * (D ** -0.5)),
            "b1": _w((lambda *s: torch.randn(*s, dtype=torch.bfloat16) * 0.4)(F)),
            "w2": _w((lambda *s: torch.randn(*s, dtype=torch.bfloat16) * 0.05)(F, D) * (F ** -0.5)),
            "b2": _w((lambda *s: torch.randn(*s, dtype=torch.bfloat16) * 0.05)(D)),
        }
    _B_in = _B_setup()

    return {
        "A_x": _A_in["x"],
        "A_dft_seq_re": _A_in["dft_seq_re"],
        "A_dft_seq_im": _A_in["dft_seq_im"],
        "A_dft_hid_re": _A_in["dft_hid_re"],
        "A_dft_hid_im": _A_in["dft_hid_im"],
        "B_x": _B_in["x"],
        "B_w1": _B_in["w1"],
        "B_b1": _B_in["b1"],
        "B_w2": _B_in["w2"],
        "B_b2": _B_in["b2"],
    }

def reference(A_x, A_dft_seq_re, A_dft_seq_im, A_dft_hid_re, A_dft_hid_im, B_x, B_w1, B_b1, B_w2, B_b2):
    def _A_ref(x, dft_seq_re, dft_seq_im, dft_hid_re, dft_hid_im):
        a = torch.einsum("bsd,ed->bse", x, dft_hid_re)
        b = torch.einsum("bsd,ed->bse", x, dft_hid_im)
        y = torch.einsum("ts,bse->bte", dft_seq_re, a) - torch.einsum("ts,bse->bte", dft_seq_im, b)
        return y

    def _B_ref(x, w1, b1, w2, b2):
        y = _layernorm(x, axis=-1)
        h = _gelu(torch.einsum("bsd,df->bsf", y, w1) + b1)
        return torch.einsum("bsf,fd->bsd", h, w2) + b2

    x = A_x
    xn = _layernorm(x, axis=-1)
    s = _A_ref(xn, A_dft_seq_re, A_dft_seq_im, A_dft_hid_re, A_dft_hid_im)
    g = _silu(_B_ref(xn, B_w1, B_b1, B_w2, B_b2))
    return x + s * g
```

```cpp
#include <cuda_runtime.h>
#include <cuda.h>
#include <cuda_bf16.h>
#include <stdint.h>
#include <type_traits>

namespace {

template <int TB, int OA, int OB> __device__ __forceinline__ void wgmma_n64(float (&d)[64], uint32_t da, uint32_t db) {
  asm volatile("{\n.reg .b64 a, b;\n.reg .b32 t, u;\nadd.s32 t, %32, %35;\nadd.s32 u, %33, %36;\n"
    "mov.b64 a, {t, 0x40000040};\nmov.b64 b, {u, 0x40000040};\n"
    "wgmma.mma_async.sync.aligned.m64n64k16.f32.bf16.bf16 "
    "{%0,%1,%2,%3,%4,%5,%6,%7,%8,%9,%10,%11,%12,%13,%14,%15,"
    "%16,%17,%18,%19,%20,%21,%22,%23,%24,%25,%26,%27,%28,%29,%30,%31}, "
    "a, b, 1, 1, 1, 0, %34;\n}\n"
    : "+f"(d[0]), "+f"(d[1]), "+f"(d[2]), "+f"(d[3]), "+f"(d[4]), "+f"(d[5]), "+f"(d[6]), "+f"(d[7]),
      "+f"(d[8]), "+f"(d[9]), "+f"(d[10]), "+f"(d[11]), "+f"(d[12]), "+f"(d[13]), "+f"(d[14]), "+f"(d[15]),
      "+f"(d[16]), "+f"(d[17]), "+f"(d[18]), "+f"(d[19]), "+f"(d[20]), "+f"(d[21]), "+f"(d[22]), "+f"(d[23]),
      "+f"(d[24]), "+f"(d[25]), "+f"(d[26]), "+f"(d[27]), "+f"(d[28]), "+f"(d[29]), "+f"(d[30]), "+f"(d[31])
    : "r"(da), "r"(db), "n"(TB), "n"(OA), "n"(OB));
}
template <int TB, int OA, int OB> __device__ __forceinline__ void wgmma_n96(float (&d)[48], uint32_t da, uint32_t db) {
  asm volatile("{\n.reg .b64 a, b;\n.reg .b32 t, u;\nadd.s32 t, %48, %51;\nadd.s32 u, %49, %52;\n"
    "mov.b64 a, {t, 0x40000040};\nmov.b64 b, {u, 0x40000040};\n"
    "wgmma.mma_async.sync.aligned.m64n96k16.f32.bf16.bf16 "
    "{%0,%1,%2,%3,%4,%5,%6,%7,%8,%9,%10,%11,%12,%13,%14,%15,"
    "%16,%17,%18,%19,%20,%21,%22,%23,%24,%25,%26,%27,%28,%29,%30,%31,"
    "%32,%33,%34,%35,%36,%37,%38,%39,%40,%41,%42,%43,%44,%45,%46,%47}, "
    "a, b, 1, 1, 1, 0, %50;\n}\n"
    : "+f"(d[0]), "+f"(d[1]), "+f"(d[2]), "+f"(d[3]), "+f"(d[4]), "+f"(d[5]), "+f"(d[6]), "+f"(d[7]),
      "+f"(d[8]), "+f"(d[9]), "+f"(d[10]), "+f"(d[11]), "+f"(d[12]), "+f"(d[13]), "+f"(d[14]), "+f"(d[15]),
      "+f"(d[16]), "+f"(d[17]), "+f"(d[18]), "+f"(d[19]), "+f"(d[20]), "+f"(d[21]), "+f"(d[22]), "+f"(d[23]),
      "+f"(d[24]), "+f"(d[25]), "+f"(d[26]), "+f"(d[27]), "+f"(d[28]), "+f"(d[29]), "+f"(d[30]), "+f"(d[31]),
      "+f"(d[32]), "+f"(d[33]), "+f"(d[34]), "+f"(d[35]), "+f"(d[36]), "+f"(d[37]), "+f"(d[38]), "+f"(d[39]),
      "+f"(d[40]), "+f"(d[41]), "+f"(d[42]), "+f"(d[43]), "+f"(d[44]), "+f"(d[45]), "+f"(d[46]), "+f"(d[47])
    : "r"(da), "r"(db), "n"(TB), "n"(OA), "n"(OB));
}
template <int TB, int OA, int OB> __device__ __forceinline__ void wgmma_n96_z(float (&d)[48], uint32_t da, uint32_t db) {
  asm volatile("{\n.reg .b64 a, b;\n.reg .b32 t, u;\nadd.s32 t, %48, %51;\nadd.s32 u, %49, %52;\n"
    "mov.b64 a, {t, 0x40000040};\nmov.b64 b, {u, 0x40000040};\n"
    "wgmma.mma_async.sync.aligned.m64n96k16.f32.bf16.bf16 "
    "{%0,%1,%2,%3,%4,%5,%6,%7,%8,%9,%10,%11,%12,%13,%14,%15,"
    "%16,%17,%18,%19,%20,%21,%22,%23,%24,%25,%26,%27,%28,%29,%30,%31,"
    "%32,%33,%34,%35,%36,%37,%38,%39,%40,%41,%42,%43,%44,%45,%46,%47}, "
    "a, b, 0, 1, 1, 0, %50;\n}\n"
    : "=f"(d[0]), "=f"(d[1]), "=f"(d[2]), "=f"(d[3]), "=f"(d[4]), "=f"(d[5]), "=f"(d[6]), "=f"(d[7]),
      "=f"(d[8]), "=f"(d[9]), "=f"(d[10]), "=f"(d[11]), "=f"(d[12]), "=f"(d[13]), "=f"(d[14]), "=f"(d[15]),
      "=f"(d[16]), "=f"(d[17]), "=f"(d[18]), "=f"(d[19]), "=f"(d[20]), "=f"(d[21]), "=f"(d[22]), "=f"(d[23]),
      "=f"(d[24]), "=f"(d[25]), "=f"(d[26]), "=f"(d[27]), "=f"(d[28]), "=f"(d[29]), "=f"(d[30]), "=f"(d[31]),
      "=f"(d[32]), "=f"(d[33]), "=f"(d[34]), "=f"(d[35]), "=f"(d[36]), "=f"(d[37]), "=f"(d[38]), "=f"(d[39]),
      "=f"(d[40]), "=f"(d[41]), "=f"(d[42]), "=f"(d[43]), "=f"(d[44]), "=f"(d[45]), "=f"(d[46]), "=f"(d[47])
    : "r"(da), "r"(db), "n"(TB), "n"(OA), "n"(OB));
}
template <int TB, int OA, int OB> __device__ __forceinline__ void wgmma_n128(float (&d)[64], uint32_t da, uint32_t db) {
  asm volatile("{\n.reg .b64 a, b;\n.reg .b32 t, u;\nadd.s32 t, %64, %67;\nadd.s32 u, %65, %68;\n"
    "mov.b64 a, {t, 0x40000040};\nmov.b64 b, {u, 0x40000040};\n"
    "wgmma.mma_async.sync.aligned.m64n128k16.f32.bf16.bf16 "
    "{%0,%1,%2,%3,%4,%5,%6,%7,%8,%9,%10,%11,%12,%13,%14,%15,"
    "%16,%17,%18,%19,%20,%21,%22,%23,%24,%25,%26,%27,%28,%29,%30,%31,"
    "%32,%33,%34,%35,%36,%37,%38,%39,%40,%41,%42,%43,%44,%45,%46,%47,"
    "%48,%49,%50,%51,%52,%53,%54,%55,%56,%57,%58,%59,%60,%61,%62,%63}, "
    "a, b, 1, 1, 1, 0, %66;\n}\n"
    : "+f"(d[0]), "+f"(d[1]), "+f"(d[2]), "+f"(d[3]), "+f"(d[4]), "+f"(d[5]), "+f"(d[6]), "+f"(d[7]),
      "+f"(d[8]), "+f"(d[9]), "+f"(d[10]), "+f"(d[11]), "+f"(d[12]), "+f"(d[13]), "+f"(d[14]), "+f"(d[15]),
      "+f"(d[16]), "+f"(d[17]), "+f"(d[18]), "+f"(d[19]), "+f"(d[20]), "+f"(d[21]), "+f"(d[22]), "+f"(d[23]),
      "+f"(d[24]), "+f"(d[25]), "+f"(d[26]), "+f"(d[27]), "+f"(d[28]), "+f"(d[29]), "+f"(d[30]), "+f"(d[31]),
      "+f"(d[32]), "+f"(d[33]), "+f"(d[34]), "+f"(d[35]), "+f"(d[36]), "+f"(d[37]), "+f"(d[38]), "+f"(d[39]),
      "+f"(d[40]), "+f"(d[41]), "+f"(d[42]), "+f"(d[43]), "+f"(d[44]), "+f"(d[45]), "+f"(d[46]), "+f"(d[47]),
      "+f"(d[48]), "+f"(d[49]), "+f"(d[50]), "+f"(d[51]), "+f"(d[52]), "+f"(d[53]), "+f"(d[54]), "+f"(d[55]),
      "+f"(d[56]), "+f"(d[57]), "+f"(d[58]), "+f"(d[59]), "+f"(d[60]), "+f"(d[61]), "+f"(d[62]), "+f"(d[63])
    : "r"(da), "r"(db), "n"(TB), "n"(OA), "n"(OB));
}
template <int TB, int OA, int OB> __device__ __forceinline__ void wgmma_n128_z(float (&d)[64], uint32_t da, uint32_t db) {
  asm volatile("{\n.reg .b64 a, b;\n.reg .b32 t, u;\nadd.s32 t, %64, %67;\nadd.s32 u, %65, %68;\n"
    "mov.b64 a, {t, 0x40000040};\nmov.b64 b, {u, 0x40000040};\n"
    "wgmma.mma_async.sync.aligned.m64n128k16.f32.bf16.bf16 "
    "{%0,%1,%2,%3,%4,%5,%6,%7,%8,%9,%10,%11,%12,%13,%14,%15,"
    "%16,%17,%18,%19,%20,%21,%22,%23,%24,%25,%26,%27,%28,%29,%30,%31,"
    "%32,%33,%34,%35,%36,%37,%38,%39,%40,%41,%42,%43,%44,%45,%46,%47,"
    "%48,%49,%50,%51,%52,%53,%54,%55,%56,%57,%58,%59,%60,%61,%62,%63}, "
    "a, b, 0, 1, 1, 0, %66;\n}\n"
    : "=f"(d[0]), "=f"(d[1]), "=f"(d[2]), "=f"(d[3]), "=f"(d[4]), "=f"(d[5]), "=f"(d[6]), "=f"(d[7]),
      "=f"(d[8]), "=f"(d[9]), "=f"(d[10]), "=f"(d[11]), "=f"(d[12]), "=f"(d[13]), "=f"(d[14]), "=f"(d[15]),
      "=f"(d[16]), "=f"(d[17]), "=f"(d[18]), "=f"(d[19]), "=f"(d[20]), "=f"(d[21]), "=f"(d[22]), "=f"(d[23]),
      "=f"(d[24]), "=f"(d[25]), "=f"(d[26]), "=f"(d[27]), "=f"(d[28]), "=f"(d[29]), "=f"(d[30]), "=f"(d[31]),
      "=f"(d[32]), "=f"(d[33]), "=f"(d[34]), "=f"(d[35]), "=f"(d[36]), "=f"(d[37]), "=f"(d[38]), "=f"(d[39]),
      "=f"(d[40]), "=f"(d[41]), "=f"(d[42]), "=f"(d[43]), "=f"(d[44]), "=f"(d[45]), "=f"(d[46]), "=f"(d[47]),
      "=f"(d[48]), "=f"(d[49]), "=f"(d[50]), "=f"(d[51]), "=f"(d[52]), "=f"(d[53]), "=f"(d[54]), "=f"(d[55]),
      "=f"(d[56]), "=f"(d[57]), "=f"(d[58]), "=f"(d[59]), "=f"(d[60]), "=f"(d[61]), "=f"(d[62]), "=f"(d[63])
    : "r"(da), "r"(db), "n"(TB), "n"(OA), "n"(OB));
}

}

namespace {

constexpr int SEQ = 2048, DM = 512, FF = 1792;
constexpr int NCTA = 128;

constexpr int CELL = 16384, NCELL = 13, NFULL = 8;
constexpr int STG_OFF = NCELL * CELL;
constexpr int CSA_OFF = STG_OFF + 16384;
constexpr int CSB_OFF = CSA_OFF + 512;
constexpr int B2_OFF = CSB_OFF + 1792;
constexpr int BAR_OFF = B2_OFF + 256;
constexpr int BAR_FULL = BAR_OFF, BAR_EMPTY = BAR_FULL + 8 * NFULL,
              BAR_CSA = BAR_EMPTY + 8 * NCELL, BAR_CSB = BAR_CSA + 8, BAR_X = BAR_CSB + 16, BAR_DEP = BAR_X + 8,
              BAR_XALL = BAR_DEP + 48, BAR_PEER = BAR_XALL + 8, BAR_STG = BAR_PEER + 8, BAR_RED = BAR_STG + 8;
constexpr int SMEM_BYTES = BAR_RED + 16;
static_assert(BAR_FULL % 64 == 0 && SMEM_BYTES <= 232448, "smem");

constexpr int NH1 = 96, NH2 = 128;
constexpr int DLT = 4;
constexpr int S1 = 32 - DLT;
constexpr int Q_H1 = 8, Q_H2 = 16, Q_S1 = 24, Q_M = Q_S1 + S1, Q_HALF = Q_M + 14;
constexpr int XA = 5;
constexpr int EA_START = 4, EA_RATE = 4;
constexpr int GV_START = 2, GV_RATE = 4;
constexpr int PF_S = 6;

struct Maps { CUtensorMap x, H[2], w1, S[2], abL, hL, w2, abS, hS; };
struct Sync {
  unsigned cnt[128 * 32];
  unsigned epoch[(NCTA + 4) * 32];
  uint4 stat[SEQ];
  float csA[2 * DM];
  float csB[FF];
};

}

__device__ __nv_bfloat16 g_ab[2 * SEQ * DM];
__device__ __nv_bfloat16 g_h[SEQ * FF];
__device__ Sync g_sync;
__device__ uint4 g_part[NCTA][8][256];

namespace {

constexpr int CNT_AB = 0, CNT_H = 64, CNT_H2 = 96;

__device__ __forceinline__ uint32_t smem_u32(const void* p) { return (uint32_t)__cvta_generic_to_shared(p); }
__device__ __forceinline__ void mbar_init(uint32_t bar, uint32_t cnt) {
  asm volatile("mbarrier.init.shared::cta.b64 [%0], %1;" ::"r"(bar), "r"(cnt) : "memory");
}
__device__ __forceinline__ void mbar_arrive_tx(uint32_t bar, uint32_t bytes) {
  asm volatile("mbarrier.arrive.expect_tx.shared::cta.b64 _, [%0], %1;" ::"r"(bar), "r"(bytes) : "memory");
}
__device__ __forceinline__ void mbar_expect_tx(uint32_t bar, uint32_t bytes) {
  asm volatile("mbarrier.expect_tx.shared::cta.b64 [%0], %1;" ::"r"(bar), "r"(bytes) : "memory");
}
__device__ __forceinline__ void mbar_arrive(uint32_t bar) {
  asm volatile("mbarrier.arrive.shared::cta.b64 _, [%0];" ::"r"(bar) : "memory");
}
__device__ __forceinline__ void mbar_arrive_cluster(uint32_t bar) {
  asm volatile("mbarrier.arrive.shared::cluster.b64 _, [%0];" ::"r"(bar) : "memory");
}
__device__ __forceinline__ uint32_t mapa(uint32_t addr, uint32_t cta) {
  uint32_t r;
  asm("mapa.shared::cluster.u32 %0, %1, %2;" : "=r"(r) : "r"(addr), "r"(cta));
  return r;
}
__device__ __forceinline__ void mbar_wait(uint32_t bar, uint32_t parity) {
  asm volatile(
      "{\n.reg .pred p;\n.reg .u32 it;\n"
      "mbarrier.try_wait.parity.shared::cta.b64 p, [%0], %1;\n@p bra LD;\nmov.u32 it, 0;\n"
      "LW:\nmbarrier.try_wait.parity.shared::cta.b64 p, [%0], %1;\n@p bra LD;\n"
      "add.u32 it, it, 1;\nsetp.lt.u32 p, it, 1048576;\n@p bra LW;\ntrap;\nLD:\n}"
      ::"r"(bar), "r"(parity) : "memory");
}
__device__ __forceinline__ bool elect_one() {
  uint32_t p;
  asm volatile("{\n.reg .pred p;\nelect.sync _|p, 0xffffffff;\nselp.u32 %0, 1, 0, p;\n}" : "=r"(p));
  return p;
}
__device__ __forceinline__ void tma_load(uint32_t dst, const CUtensorMap* m, int c0, int c1, uint32_t bar) {
  asm volatile("cp.async.bulk.tensor.2d.shared::cluster.global.mbarrier::complete_tx::bytes [%0], [%1, {%3, %4}], [%2];"
               ::"r"(dst), "l"((uint64_t)m), "r"(bar), "r"(c0), "r"(c1) : "memory");
}
__device__ __forceinline__ void tma_load_mc(uint32_t dst, const CUtensorMap* m, int c0, int c1, uint32_t bar) {
  asm volatile("cp.async.bulk.tensor.2d.shared::cluster.global.mbarrier::complete_tx::bytes.multicast::cluster [%0], [%1, {%3, %4}], [%2], %5;"
               ::"r"(dst), "l"((uint64_t)m), "r"(bar), "r"(c0), "r"(c1), "h"((uint16_t)3) : "memory");
}
__device__ __forceinline__ void tma_load_mc_hint(uint32_t dst, const CUtensorMap* m, int c0, int c1, uint32_t bar, uint64_t pol) {
  asm volatile("cp.async.bulk.tensor.2d.shared::cluster.global.mbarrier::complete_tx::bytes.multicast::cluster.L2::cache_hint [%0], [%1, {%3, %4}], [%2], %5, %6;"
               ::"r"(dst), "l"((uint64_t)m), "r"(bar), "r"(c0), "r"(c1), "h"((uint16_t)3), "l"(pol) : "memory");
}
__device__ __forceinline__ void tma_store(const CUtensorMap* m, uint32_t src, int c0, int c1) {
  asm volatile("cp.async.bulk.tensor.2d.global.shared::cta.bulk_group [%0, {%2, %3}], [%1];"
               ::"l"((uint64_t)m), "r"(src), "r"(c0), "r"(c1) : "memory");
  asm volatile("cp.async.bulk.commit_group;" ::: "memory");
}
__device__ __forceinline__ void cp_async16(uint32_t dst, const void* src) {
  asm volatile("cp.async.cg.shared.global [%0], [%1], 16;" ::"r"(dst), "l"(src) : "memory");
}
__device__ __forceinline__ void prefetch_map(const CUtensorMap* m) {
  asm volatile("prefetch.tensormap [%0];" ::"l"((uint64_t)m) : "memory");
}
__device__ __forceinline__ void prefetch_l2(const void* p, uint32_t bytes) {
  asm volatile("cp.async.bulk.prefetch.L2.global [%0], %1;" ::"l"(p), "r"(bytes) : "memory");
}
__device__ __forceinline__ unsigned ld_relaxed(const unsigned* p) {
  unsigned v;
  asm volatile("ld.relaxed.gpu.global.u32 %0, [%1];" : "=r"(v) : "l"(p) : "memory");
  return v;
}
__device__ __forceinline__ void red_add(unsigned* p) {
  asm volatile("red.relaxed.gpu.global.add.u32 [%0], 1;" ::"l"(p) : "memory");
}
__device__ __forceinline__ uint32_t tagf(float v, uint32_t tag) { return (__float_as_uint(v) & ~1u) | tag; }
__device__ __forceinline__ void st_tag1(void* p, float a, uint32_t tag) {
  asm volatile("st.relaxed.gpu.global.u32 [%0], %1;" ::"l"(p), "r"(tagf(a, tag)) : "memory");
}
__device__ __forceinline__ void st_tag2(void* p, float a, float b, uint32_t tag) {
  asm volatile("{\n.reg .b64 v;\nmov.b64 v, {%1,%2};\nst.relaxed.gpu.global.b64 [%0], v;\n}"
               ::"l"(p), "r"(tagf(a, tag)), "f"(b) : "memory");
}
__device__ __forceinline__ void st_raw4(void* p, uint32_t a, uint32_t b, uint32_t c, uint32_t d) {
  asm volatile("st.relaxed.gpu.global.v4.u32 [%0], {%1,%2,%3,%4};" ::"l"(p), "r"(a), "r"(b), "r"(c), "r"(d) : "memory");
}
#define LD128 ".reg .b128 v;\n.reg .b64 l, h;\nld.relaxed.gpu.global.b128 v, [%4];\nmov.b128 {l, h}, v;\nmov.b64 {%0,%1}, l;\nmov.b64 {%2,%3}, h;\n"
__device__ __forceinline__ uint4 ld_gpu4(const void* p) {
  uint4 v;
  asm volatile("{\n" LD128 "}" : "=r"(v.x), "=r"(v.y), "=r"(v.z), "=r"(v.w) : "l"(p) : "memory");
  return v;
}
__device__ __forceinline__ uint2 ld_gpu2(const void* p) {
  uint2 v;
  asm volatile("{\n.reg .b64 v;\nld.relaxed.gpu.global.b64 v, [%2];\nmov.b64 {%0,%1}, v;\n}" : "=r"(v.x), "=r"(v.y) : "l"(p) : "memory");
  return v;
}
__device__ __forceinline__ void settle_all(uint4& v, const void* p, uint32_t ntag) {
  asm volatile(
      "{\n.reg .pred p;\n.reg .u32 t, u, it;\nmov.u32 it, 0;\n"
      "LW:\nxor.b32 t, %0, %5;\nxor.b32 u, %1, %5;\nand.b32 t, t, u;\nxor.b32 u, %2, %5;\nand.b32 t, t, u;\n"
      "xor.b32 u, %3, %5;\nand.b32 t, t, u;\nand.b32 t, t, 1;\nsetp.ne.u32 p, t, 0;\n@p bra LD;\n"
      "setp.ne.u32 p, it, 0;\n@p nanosleep.u32 60;\n{\n" LD128 "}\n"
      "add.u32 it, it, 1;\nsetp.lt.u32 p, it, 1048576;\n@p bra LW;\ntrap;\nLD:\n}"
      : "+&r"(v.x), "+&r"(v.y), "+&r"(v.z), "+&r"(v.w) : "l"(p), "r"(ntag) : "memory");
}
template <int N> __device__ void settle(uint4* v, const void* p, uint32_t ntag);
template <> __device__ __forceinline__ void settle<2>(uint4* v, const void* p, uint32_t ntag) {
  asm volatile(
      "{\n.reg .pred p;\n.reg .u32 t, u, it;\n.reg .b128 v;\n.reg .b64 l, h;\nmov.u32 it, 0;\n"
      "LW:\nxor.b32 t, %0, %9;\nxor.b32 u, %4, %9;\nand.b32 t, t, u;\n"
      "and.b32 t, t, 1;\nsetp.ne.u32 p, t, 0;\n@p bra LD;\nsetp.ne.u32 p, it, 0;\n@p nanosleep.u32 40;\n"
      "ld.relaxed.gpu.global.b128 v, [%8+0];\nmov.b128 {l, h}, v;\nmov.b64 {%0,%1}, l;\nmov.b64 {%2,%3}, h;\n"
      "ld.relaxed.gpu.global.b128 v, [%8+128];\nmov.b128 {l, h}, v;\nmov.b64 {%4,%5}, l;\nmov.b64 {%6,%7}, h;\n"
      "add.u32 it, it, 1;\nsetp.lt.u32 p, it, 1048576;\n@p bra LW;\ntrap;\nLD:\n}"
      : "+&r"(v[0].x), "+&r"(v[0].y), "+&r"(v[0].z), "+&r"(v[0].w), "+&r"(v[1].x), "+&r"(v[1].y), "+&r"(v[1].z), "+&r"(v[1].w)
      : "l"(p), "r"(ntag) : "memory");
}
template <> __device__ __forceinline__ void settle<4>(uint4* v, const void* p, uint32_t ntag) {
  asm volatile(
      "{\n.reg .pred p;\n.reg .u32 t, u, it;\n.reg .b128 v;\n.reg .b64 l, h;\nmov.u32 it, 0;\n"
      "LW:\nxor.b32 t, %0, %17;\n"
      "xor.b32 u, %4, %17;\nand.b32 t, t, u;\n"
      "xor.b32 u, %8, %17;\nand.b32 t, t, u;\n"
      "xor.b32 u, %12, %17;\nand.b32 t, t, u;\n"
      "and.b32 t, t, 1;\nsetp.ne.u32 p, t, 0;\n@p bra LD;\nsetp.ne.u32 p, it, 0;\n@p nanosleep.u32 40;\n"
      "ld.relaxed.gpu.global.b128 v, [%16+0];\nmov.b128 {l, h}, v;\nmov.b64 {%0,%1}, l;\nmov.b64 {%2,%3}, h;\n"
      "ld.relaxed.gpu.global.b128 v, [%16+512];\nmov.b128 {l, h}, v;\nmov.b64 {%4,%5}, l;\nmov.b64 {%6,%7}, h;\n"
      "ld.relaxed.gpu.global.b128 v, [%16+1024];\nmov.b128 {l, h}, v;\nmov.b64 {%8,%9}, l;\nmov.b64 {%10,%11}, h;\n"
      "ld.relaxed.gpu.global.b128 v, [%16+1536];\nmov.b128 {l, h}, v;\nmov.b64 {%12,%13}, l;\nmov.b64 {%14,%15}, h;\n"
      "add.u32 it, it, 1;\nsetp.lt.u32 p, it, 1048576;\n@p bra LW;\ntrap;\nLD:\n}"
      : "+&r"(v[0].x), "+&r"(v[0].y), "+&r"(v[0].z), "+&r"(v[0].w), "+&r"(v[1].x), "+&r"(v[1].y), "+&r"(v[1].z), "+&r"(v[1].w), "+&r"(v[2].x), "+&r"(v[2].y), "+&r"(v[2].z), "+&r"(v[2].w), "+&r"(v[3].x), "+&r"(v[3].y), "+&r"(v[3].z), "+&r"(v[3].w)
      : "l"(p), "r"(ntag) : "memory");
}
__device__ __forceinline__ void settle2(uint2& v, const void* p, uint32_t ntag) {
  asm volatile(
      "{\n.reg .pred p;\n.reg .u32 t, it;\n.reg .b64 w;\nmov.u32 it, 0;\n"
      "LW:\nxor.b32 t, %0, %3;\nand.b32 t, t, 1;\nsetp.ne.u32 p, t, 0;\n@p bra LD;\nsetp.ne.u32 p, it, 0;\n@p nanosleep.u32 40;\n"
      "ld.relaxed.gpu.global.b64 w, [%2];\nmov.b64 {%0,%1}, w;\n"
      "add.u32 it, it, 1;\nsetp.lt.u32 p, it, 1048576;\n@p bra LW;\ntrap;\nLD:\n}"
      : "+&r"(v.x), "+&r"(v.y) : "l"(p), "r"(ntag) : "memory");
}
__device__ __forceinline__ void wait_count(const unsigned* p, unsigned target) {
  asm volatile(
      "{\n.reg .pred p;\n.reg .u32 it, v;\nmov.u32 it, 0;\n"
      "LW:\nld.acquire.gpu.global.u32 v, [%0];\nsub.u32 v, v, %1;\nsetp.ge.s32 p, v, 0;\n@p bra LD;\nnanosleep.u32 60;\n"
      "add.u32 it, it, 1;\nsetp.lt.u32 p, it, 1048576;\n@p bra LW;\ntrap;\nLD:\n}"
      ::"l"(p), "r"(target) : "memory");
}
__device__ __forceinline__ void fence_async_smem() { asm volatile("fence.proxy.async.shared::cta;" ::: "memory"); }
__device__ __forceinline__ void wg_fence() { asm volatile("wgmma.fence.sync.aligned;" ::: "memory"); }
__device__ __forceinline__ void wg_commit() { asm volatile("wgmma.commit_group.sync.aligned;" ::: "memory"); }
template <int N> __device__ __forceinline__ void wg_wait() { asm volatile("wgmma.wait_group.sync.aligned %0;" ::"n"(N) : "memory"); }
template <int A, int B, int L> __device__ __forceinline__ void pin(float (&d)[L]) {
#pragma unroll
  for (int i = A; i < B; i++) asm volatile("" : "+f"(d[i])::"memory");
}
__device__ __forceinline__ uint32_t pack_bf16(float lo, float hi) {
  uint32_t r;
  asm("cvt.rn.bf16x2.f32 %0, %1, %2;" : "=r"(r) : "f"(hi), "f"(lo));
  return r;
}
__device__ __forceinline__ uint32_t add_bf16x2(uint32_t a, uint32_t b) {
  uint32_t r;
  asm("add.rn.bf16x2 %0, %1, %2;" : "=r"(r) : "r"(a), "r"(b));
  return r;
}
__device__ __forceinline__ float bf_lo(uint32_t v) { return __uint_as_float(v << 16); }
__device__ __forceinline__ float bf_hi(uint32_t v) { return __uint_as_float(v & 0xffff0000u); }
__device__ __forceinline__ float tanh_fast(float x) {
  float r;
  asm("tanh.approx.f32 %0, %1;" : "=f"(r) : "f"(x));
  return r;
}
__device__ __forceinline__ float silu_half(float hm) { return fmaf(hm, tanh_fast(hm), hm); }
__device__ __forceinline__ void stmatrix2(uint32_t addr, uint32_t r0, uint32_t r1) {
  asm volatile("stmatrix.sync.aligned.m8n8.x2.shared.b16 [%0], {%1,%2};" ::"r"(addr), "r"(r0), "r"(r1) : "memory");
}
__device__ __forceinline__ void stmatrix4(uint32_t addr, uint32_t r0, uint32_t r1, uint32_t r2, uint32_t r3) {
  asm volatile("stmatrix.sync.aligned.m8n8.x4.shared.b16 [%0], {%1,%2,%3,%4};" ::"r"(addr), "r"(r0), "r"(r1), "r"(r2), "r"(r3) : "memory");
}
__device__ __forceinline__ void ldmatrix4(uint32_t addr, uint32_t* r) {
  asm volatile("ldmatrix.sync.aligned.m8n8.x4.shared.b16 {%0,%1,%2,%3}, [%4];" : "=r"(r[0]), "=r"(r[1]), "=r"(r[2]), "=r"(r[3]) : "r"(addr) : "memory");
}
__device__ __forceinline__ void sts32(uint32_t addr, float v) {
  asm volatile("st.shared.f32 [%0], %1;" ::"r"(addr), "f"(v) : "memory");
}
__device__ __forceinline__ uint4 lds128(uint32_t addr) {
  uint4 v;
  asm volatile("ld.shared.v4.u32 {%0,%1,%2,%3}, [%4];" : "=r"(v.x), "=r"(v.y), "=r"(v.z), "=r"(v.w) : "r"(addr) : "memory");
  return v;
}
__device__ __forceinline__ float4 lds128f(uint32_t addr) {
  float4 v;
  asm volatile("ld.shared.v4.f32 {%0,%1,%2,%3}, [%4];" : "=f"(v.x), "=f"(v.y), "=f"(v.z), "=f"(v.w) : "r"(addr));
  return v;
}
__device__ __forceinline__ float2 lds64f(uint32_t addr) {
  float2 v;
  asm volatile("ld.shared.v2.f32 {%0,%1}, [%2];" : "=f"(v.x), "=f"(v.y) : "r"(addr));
  return v;
}
__device__ __forceinline__ uint4 ldg128(const void* p) {
  uint4 v;
  asm volatile("ld.relaxed.gpu.global.v4.u32 {%0,%1,%2,%3}, [%4];" : "=r"(v.x), "=r"(v.y), "=r"(v.z), "=r"(v.w) : "l"(p) : "memory");
  return v;
}
__device__ __forceinline__ float sum8(uint4 v) {
  return ((bf_lo(v.x) + bf_hi(v.x)) + (bf_lo(v.y) + bf_hi(v.y))) + ((bf_lo(v.z) + bf_hi(v.z)) + (bf_lo(v.w) + bf_hi(v.w)));
}
__device__ __forceinline__ float sq8(uint4 v) {
  const float a = fmaf(bf_lo(v.x), bf_lo(v.x), bf_hi(v.x) * bf_hi(v.x)), b = fmaf(bf_lo(v.y), bf_lo(v.y), bf_hi(v.y) * bf_hi(v.y));
  return fmaf(bf_lo(v.z), bf_lo(v.z), fmaf(bf_hi(v.z), bf_hi(v.z), a)) + fmaf(bf_lo(v.w), bf_lo(v.w), fmaf(bf_hi(v.w), bf_hi(v.w), b));
}
constexpr uint64_t EVICT_FIRST = 0x12F0000000000000ull;
constexpr int LBO_K = 1 << 16, LBO_MN = 512 << 16;

constexpr uint64_t RING = 0xb7a69584c3210ull;
__host__ __device__ constexpr int ring(int p) { return (int)(RING >> (4 * p) & 15); }
constexpr int NF = Q_HALF - Q_S1, NT = 2 * DLT;
struct TailPlan { uint64_t a, b, rel, par; };
constexpr TailPlan tail_plan() {
  int cell[13 + 2 * NT] = {}, freed[13 + 2 * NT] = {}, n = 0, used = 0, bc = 0;
  for (int x = 2 * NF - 13; x < 2 * NF; x++) { cell[n] = ring(x % 13); freed[n++] = x / 2; }
  TailPlan p = {};
  for (int u = 0; u < NT; u++) {
    const int a = cell[used++];
    if (!(u & 1)) bc = cell[used++];
    const int r = freed[used - 1];
    p.a |= (uint64_t)a << 4 * u; p.b |= (uint64_t)bc << 4 * u;
    p.rel |= (uint64_t)(r % 6) << 4 * u; p.par |= (uint64_t)((r / 6 + 1) & 1) << 4 * u;
    cell[n] = a; freed[n++] = NF + u;
    if (u & 1) { cell[n] = bc; freed[n++] = NF + u; }
  }
  return p;
}
constexpr TailPlan TP = tail_plan();
static_assert(NT == 8, "all tail stages in flight, each waits for a release of the last lap");
__host__ __device__ constexpr int tail_a(int u) { return (int)(TailPlan(TP).a >> (4 * u) & 15) * CELL; }
__host__ __device__ constexpr int tail_b(int u) { return (int)(TailPlan(TP).b >> (4 * u) & 15) * CELL + (u & 1) * 8192; }
__host__ __device__ constexpr int cell_a(int q) { return q < Q_S1 ? (q & 7) : ring((2 * (q - Q_S1)) % 13); }
__host__ __device__ constexpr int cell_b(int q) { return q < Q_S1 ? 8 + q % 5 : ring((2 * (q - Q_S1) + 1) % 13); }
__host__ __device__ constexpr int off_a(int q) { return (q < Q_HALF ? cell_a(q) * CELL : tail_a(q - Q_HALF)) >> 4; }
__host__ __device__ constexpr int off_b(int q) {
  return ((q < Q_HALF ? cell_b(q) * CELL : tail_b(q - Q_HALF)) >> 4) + (q >= Q_H1 ? LBO_MN : LBO_K);
}
__host__ __device__ constexpr int full_parity(int q) { return ((q >> 3) ^ ((q & 7) == 0)) & 1; }
__host__ __device__ constexpr int sched(int k, int start, int rate, int total) {
  return k < start ? 0 : (rate * (k + 1 - start) < total ? rate * (k + 1 - start) : total);
}
__host__ __device__ constexpr int ea_end(int k) { return sched(k, EA_START, EA_RATE, 16); }
__host__ __device__ constexpr int gv_end(int k) { return sched(k, GV_START, GV_RATE, 112); }
constexpr int EA_BLOCKS = EA_START + 16 / EA_RATE + 2;
constexpr int GV_BLOCKS = GV_START + 112 / GV_RATE + 3;
static_assert(EA_START >= 3 && EA_RATE <= 4 && gv_end(EA_BLOCKS - 12) < 4, "a|b must be staged before the first h box");
static_assert(GV_START >= 1 && gv_end(7) <= NH1 / 2 && GV_BLOCKS < 6 + S1, "GELU schedule");

template <int I, int N, class F> __device__ __forceinline__ void static_for(F&& f) {
  if constexpr (I < N) {
    f(std::integral_constant<int, I>{});
    static_for<I + 1, N>(f);
  }
}

struct Cons {
  uint32_t da, db, base, rel, lane;
  template <int Q, int N, int L> __device__ __forceinline__ void step(float (&d)[L]) {
    constexpr int TB = Q >= Q_H1, P = Q - 1;
    constexpr bool FIRST = Q == 0 || Q == Q_H1 || Q == Q_H2 || Q == Q_S1;
    if constexpr (Q == 0) {
      asm volatile("cp.async.wait_group 0;" ::: "memory");
      fence_async_smem();
      asm volatile("bar.sync 1, 256;" ::: "memory");
    } else {
      mbar_wait(base + BAR_FULL + 8 * (Q & 7), full_parity(Q));
    }
    wg_fence();
    static_for<0, 4>([&](auto K) {
      constexpr int k = decltype(K)::value;
      constexpr int oa = off_a(Q) + 2 * k, ob = off_b(Q) + (TB ? 128 : 2) * k;
      if constexpr (N == 128) { if (FIRST && k == 0) wgmma_n128_z<TB, oa, ob>(d, da, db); else wgmma_n128<TB, oa, ob>(d, da, db); }
      if constexpr (N == 96) { if (FIRST && k == 0) wgmma_n96_z<TB, oa, ob>(d, da, db); else wgmma_n96<TB, oa, ob>(d, da, db); }
      if constexpr (N == 64) wgmma_n64<TB, oa, ob>(d, da, db);
      if (k == 0) {
        wg_commit();
        if (Q > 0) wg_wait<1>();
        if (Q > 0 && P < Q_HALF && lane < 2) {
          if (P < Q_S1 - 5) mbar_arrive_cluster(rel + 8 * cell_b(P));
          if (P == Q_S1 - 7) mbar_arrive_cluster(rel);
          if constexpr (P >= Q_S1 - 5) mbar_arrive_cluster(rel + 8 * ((P - Q_S1 + 6) % 6));
        }
      }
    });
    wg_commit();
  }
  template <int Q0, int Q1> __device__ __forceinline__ void run(float (&d)[64]) {
    static_assert(Q0 > Q_S1 && Q1 <= Q_HALF, "run");
    uint32_t prev = (Q0 - 1 - Q_S1) % 6;
    constexpr int P0 = 2 * (Q0 - Q_S1) % 13;
    uint64_t rot = (RING >> (4 * P0) | RING << (52 - 4 * P0)) & ((1ull << 52) - 1);
#pragma unroll 1
    for (int q = Q0; q < Q1; q++) {
      const uint32_t a = da + ((uint32_t)rot & 15) * (CELL >> 4), b = db + ((uint32_t)rot >> 4 & 15) * (CELL >> 4);
      rot = rot >> 8 | (rot & 255) << 44;
      mbar_wait(base + BAR_FULL + 8 * (q & 7), full_parity(q));
      wg_fence();
      static_for<0, 4>([&](auto K) {
        constexpr int k = decltype(K)::value;
        wgmma_n128<1, 2 * k, LBO_MN + 128 * k>(d, a, b);
        if (k == 0) {
          wg_commit();
          wg_wait<1>();
          if (lane < 2) mbar_arrive_cluster(rel + 8 * prev);
        }
      });
      wg_commit();
      prev = prev == 5 ? 0 : prev + 1;
    }
  }
};

template <bool by_tpc>
__global__ void __cluster_dims__(2, 1, 1) __launch_bounds__(384, 1)
fused_kernel(const __nv_bfloat16* __restrict__ x, const __nv_bfloat16* __restrict__ Hre, const __nv_bfloat16* __restrict__ Him,
             Sync* sy, const __nv_bfloat16* __restrict__ w1, const __nv_bfloat16* __restrict__ b1,
             const __nv_bfloat16* __restrict__ b2, const __nv_bfloat16* __restrict__ w2, const __nv_bfloat16* __restrict__ Sre,
             const __nv_bfloat16* __restrict__ Sim, uint4* part, __nv_bfloat16* __restrict__ out,
             const __grid_constant__ Maps maps) {
  extern __shared__ __align__(1024) uint8_t smem[];
  const uint32_t base = smem_u32(smem);
  const int tid = threadIdx.x, warp = __reduce_max_sync(0xffffffffu, tid >> 5), lane = tid & 31;
  uint32_t smid;
  asm("mov.u32 %0, %%smid;" : "=r"(smid));
  const int t = by_tpc ? smid >> 1 : ((blockIdx.x >> 1) + 64) % 66;
  const int t7 = ((t - 32) * 37) >> 8;
  const int rank = blockIdx.x & 1;
  const int role = t < 32 || !by_tpc ? (t & 7) * 8 + (t >> 3) : t < 60 ? (t - 31 - 7 * t7) * 8 + 4 + t7 : t - 56;
  if (t >= 64) {
    const int hb = (t - 64) * 2 + rank;
    const uint32_t bar = base + BAR_OFF;
    auto group = [](int i) { return (0x6521430 >> (4 * i)) & 7; };
    auto fetch = [&](int i) {
      mbar_arrive_tx(bar + 8 * (i % 3), 4 * CELL);
#pragma unroll 1
      for (int r = 0; r < 8; r++)
        tma_load(base + (i % 3) * 4 * CELL + r * 8192, &maps.w1, hb * 448 + group(i) * 64, r * 64, bar + 8 * (i % 3));
    };
    __nanosleep(100);
    if (warp == 0 && elect_one()) {
      for (int i = 0; i < 3; i++) mbar_init(bar + 8 * i, 1);
      fence_async_smem();
      for (int i = 0; i < 3; i++) fetch(i);
    }
    __syncthreads();
    const unsigned ep0 = ld_relaxed(&sy->epoch[(NCTA + hb) * 32 + lane]);
#pragma unroll 1
    for (int i = 0; i < 7; i++) {
      mbar_wait(bar + 8 * (i % 3), (i / 3) & 1);
      float acc[8] = {};
#pragma unroll
      for (int r = tid >> 3; r < DM; r += 48) {
        const uint4 v = *(const uint4*)(smem + (i % 3) * 4 * CELL + r * 128 + (((tid ^ r) & 7) << 4));
        const uint32_t w[4] = {v.x, v.y, v.z, v.w};
#pragma unroll
        for (int e = 0; e < 4; e++) { acc[2 * e] += bf_lo(w[e]); acc[2 * e + 1] += bf_hi(w[e]); }
      }
#pragma unroll
      for (int e = 0; e < 8; e++) {
        acc[e] += __shfl_xor_sync(0xffffffffu, acc[e], 8);
        acc[e] += __shfl_xor_sync(0xffffffffu, acc[e], 16);
      }
      float* red = (float*)(smem + 12 * CELL + (i & 1) * 4096);
      if (lane < 8) {
        ((float4*)red)[warp * 16 + lane * 2] = make_float4(acc[0], acc[1], acc[2], acc[3]);
        ((float4*)red)[warp * 16 + lane * 2 + 1] = make_float4(acc[4], acc[5], acc[6], acc[7]);
      }
      __syncthreads();
      if (warp == 1 && i + 3 < 7 && elect_one()) fetch(i + 3);
      if (warp == 0) {
        float2 a = make_float2(0.f, 0.f);
#pragma unroll
        for (int g = 0; g < 12; g++) { a.x += red[g * 64 + lane * 2]; a.y += red[g * 64 + lane * 2 + 1]; }
        st_tag2(&sy->csB[hb * 448 + group(i) * 64 + lane * 2], a.x, a.y, ~ep0 & 1);
      }
    }
    if (warp == 0) sy->epoch[(NCTA + hb) * 32 + lane] = ep0 + 1;
    return;
  }
  const int bid = role * 2 + rank, u = role >> 3;
  const int j1 = role & 7, ib1 = u * 2 + rank, kh1 = j1 >> 2, n1 = j1 & 3;
  const int kh = u >> 2, ib = (u & 1) * 8 + j1, n = (u & 2) + rank;
  const int ckeep = n * 128 + kh * 64;

  if (warp >= 8) {
    asm volatile("setmaxnreg.dec.sync.aligned.u32 72;");
    const uint32_t half = rank * 8192, full = base + BAR_FULL, empty = base + BAR_EMPTY;
    if (elect_one()) {
      if (warp == 8) {
#pragma unroll
        for (int q = 1; q < 3; q++) {
          mbar_init(full + 8 * q, 1);
          mbar_arrive_tx(full + 8 * q, 2 * CELL);
          tma_load(base + q * CELL, &maps.x, q * 64, ib1 * 128, full + 8 * q);
          tma_load(base + (8 + q) * CELL, &maps.H[kh1], q * 64, n1 * 128, full + 8 * q);
          tma_load(base + (8 + q) * CELL + 8192, &maps.H[kh1], q * 64, n1 * 128 + 64, full + 8 * q);
        }
#pragma unroll
        for (int q = 3; q < 5; q++) {
          mbar_init(full + 8 * q, 1);
          mbar_expect_tx(full + 8 * q, CELL);
          tma_load(base + q * CELL, &maps.x, q * 64, ib1 * 128, full + 8 * q);
        }
      } else if (warp == 9) {
        for (int s = 8; s < NCELL; s++) mbar_init(empty + 8 * s, 16);
      } else if (warp == 10) {
        for (int s = 0; s < 11; s++) mbar_init(base + BAR_CSA + 8 * s, s ? 1 : 2);
      } else {
        for (int s = 0; s < 4; s++) mbar_init(base + BAR_PEER + 8 * s, 8);
      }
      asm volatile("fence.mbarrier_init.release.cluster;" ::: "memory");
    }
    __syncwarp();
    asm volatile("barrier.cluster.arrive.relaxed.aligned;" ::: "memory");
    if (warp == 8) asm volatile("barrier.cluster.wait.aligned;" ::: "memory");
    asm volatile("bar.sync 0;" ::: "memory");
    if (warp == 8) {
      uint32_t cb = 11, par = 1;
      auto stage1 = [&](int q, const CUtensorMap* m, int c0, int c1) {
        mbar_wait(empty + 8 * cb, par);
        if (elect_one()) {
          tma_load_mc(base + cb * CELL + half, m, c0, c1, full + 8 * (q & 7));
          mbar_arrive_tx(full + 8 * (q & 7), CELL);
        }
        if (++cb == NCELL) { cb = 8; par ^= 1; }
      };
#pragma unroll 1
      for (int q = 3; q < Q_H1; q++) {
        if (q == XA && elect_one()) {
          mbar_expect_tx(full + 8 * XA, CELL);
          tma_load(base + XA * CELL, &maps.x, XA * 64, ib1 * 128, full + 8 * XA);
          mbar_arrive_tx(base + BAR_XALL, (7 - XA) * CELL);
#pragma unroll
          for (int r = XA + 1; r < 8; r++) tma_load(base + r * CELL, &maps.x, r * 64, ib1 * 128, base + BAR_XALL);
        }
        stage1(q, &maps.H[kh1], q * 64, n1 * 128 + rank * 64);
      }
      const int wcol = j1 * 224 + rank * 64;
#pragma unroll 1
      for (int q = Q_H1; q < Q_S1; q++) stage1(q, &maps.w1, wcol + (q < Q_H2 ? 0 : NH1), (q & 7) * 64);
      const int arow = ib * 128 + rank * 64, csend = ckeep ^ 64;
      uint64_t rota = RING, rotb = RING >> 4 | (RING & 15) << 48;
      uint32_t cura = base, curb = base + ring(1) * CELL, ebar = empty, lap = 0, bara = full + 8 * (Q_S1 & 7), barb = bara;
      int ka = kh * DLT * 64, kb = kh * SEQ + ka;
      const uint32_t sbase = __reduce_max_sync(0xffffffffu, base), elast = sbase + BAR_EMPTY + 40;
      auto acquire = [&]() {
        mbar_wait(ebar, lap);
        if (ebar == elast) { ebar -= 40; lap ^= 1; } else ebar += 8;
      };
      auto send_a = [&](const CUtensorMap* m, int step) {
        if (elect_one()) tma_load_mc_hint(cura + half, m, ka, arow, bara, EVICT_FIRST);
        ka += step;
        bara = sbase + BAR_FULL + ((bara + 8) & 63);
        rota = rota >> 8 | (rota & 255) << 44;
        cura = sbase + ((uint32_t)rota & 15) * CELL;
      };
      auto send_b = [&](const CUtensorMap* m, int step) {
        if (elect_one()) {
          tma_load(curb, m, ckeep, kb, barb);
          tma_load(curb + 8192, m, csend, kb, barb);
          mbar_arrive_tx(barb, 2 * CELL);
        }
        kb += step;
        barb = sbase + BAR_FULL + ((barb + 8) & 63);
        rotb = rotb >> 8 | (rotb & 255) << 44;
        curb = sbase + ((uint32_t)rotb & 15) * CELL;
      };
      auto depend = [&](int d) {
        mbar_wait(base + BAR_DEP + 8 * d, 0);
        asm volatile("fence.proxy.async.global;" ::: "memory");
      };
#pragma unroll 1
      for (int t = 0; t < 2; t++) {
        acquire();
        send_a(&maps.S[kh], 64);
      }
      depend(0);
#pragma unroll 1
      for (int t = 0; t < 2; t++) send_b(&maps.abL, 64);
#pragma unroll 1
      for (int t = 2; t < 6; t++) {
        acquire();
        send_a(&maps.S[kh], 64);
        if (t == 4) depend(1);
        send_b(&maps.abL, 64);
      }
      send_a(&maps.S[kh], 64);
#pragma unroll 1
      for (int t = 6; t < 8; t++) {
        acquire();
        send_b(&maps.abL, 64);
        send_a(&maps.S[kh], 64);
      }
      depend(5);
#pragma unroll 1
      for (int t = 8; t < S1 - 1; t++) {
        acquire();
        send_b(&maps.abL, 64);
        send_a(&maps.S[kh], 64);
      }
      acquire();
      send_b(&maps.abL, 0);
#pragma unroll 1
      for (int sg = 0; sg < 2; sg++) {
        uint32_t skip = sg ? 0x20220 : 0x0201020;
        depend(2 + sg);
        ka = kb = kh * 896 + sg * 128;
        send_a(&maps.hL, 64 + ((skip & 15) << 6));
#pragma unroll 1
        for (int t = sg ? 5 : 7; t > 0; t--) {
          acquire();
          send_b(&maps.w2, 64 + ((skip & 15) << 6));
          skip >>= 4;
          send_a(&maps.hL, 64 + ((skip & 15) << 6));
        }
        acquire();
        send_b(&maps.w2, 0);
      }
      depend(4);
#pragma unroll 1
      for (int t = 0; t < 2 * DLT; t++) {
        constexpr uint64_t TA = TP.a, TB = TP.b, TR = TP.rel, TQ = TP.par;
        mbar_wait(empty + 8 * (uint32_t)(TR >> 4 * t & 15), (uint32_t)(TQ >> 4 * t) & 1);
        if (elect_one()) {
          const uint32_t bar = full + 8 * ((Q_HALF + t) & 7);
          const int mat = t >= DLT, k0 = (mat ? t - DLT : 32 - DLT + t) * 64;
          tma_load_mc_hint(base + (uint32_t)(TA >> 4 * t & 15) * CELL + half, &maps.S[mat], k0, arow, bar, EVICT_FIRST);
          tma_load(base + (uint32_t)(TB >> 4 * t & 15) * CELL + (t & 1) * 8192, &maps.abL, ckeep, mat * SEQ + k0, bar);
          mbar_arrive_tx(bar, CELL + 8192);
        }
      }
      mbar_wait(base + BAR_PEER, 0);
    } else {
      const unsigned ep0 = ld_relaxed(&sy->epoch[bid * 32 + lane]);
      const uint32_t tag = ~ep0 & 1;
      if (warp == 9) {
        mbar_wait(base + BAR_RED, 0);
        {
          const float4 p = *(const float4*)(smem + STG_OFF + 4608 + (lane >> 2) * 144 + (lane & 3) * 32),
                       q = *(const float4*)(smem + STG_OFF + 4608 + (lane >> 2) * 144 + (lane & 3) * 32 + 16);
          float v = ((p.x + p.y) + (p.z + p.w)) + ((q.x + q.y) + (q.z + q.w));
          v += __shfl_xor_sync(0xffffffffu, v, 1);
          v += __shfl_xor_sync(0xffffffffu, v, 2);
          if ((lane & 3) == 0) st_tag1(&sy->csA[j1 * 128 + ib1 * 8 + (lane >> 2)], v, tag);
        }
        uint4 c = make_uint4(tag ^ 1, 0, 0, 0);
        settle_all(c, &sy->csA[j1 * 128 + lane * 4], tag ^ 1);
        *(uint4*)(smem + CSA_OFF + lane * 16) = c;
        __syncwarp();
        if (lane == 0) mbar_arrive(base + BAR_CSA);
        mbar_wait(base + BAR_STG, 0);
        if (elect_one()) {
          mbar_arrive_tx(base + BAR_X, CELL);
          tma_load(base + STG_OFF, &maps.x, ckeep, ib * 128, base + BAR_X);
        }
      } else {
        const int sw = warp - 10;
        if (sw == 1 && lane == 0) {
          prefetch_map(&maps.w1); prefetch_map(&maps.S[0]); prefetch_map(&maps.S[1]); prefetch_map(&maps.abL);
          prefetch_map(&maps.hL); prefetch_map(&maps.w2); prefetch_map(&maps.abS); prefetch_map(&maps.hS);
        }
        __nanosleep(1000);
        if (sw == 0 && lane == 0) prefetch_l2(w1 + (size_t)bid * 4 * FF, 4 * FF * 2);
        if (sw == 0) {
          __nanosleep(1500);
          const __nv_bfloat16* sp = (kh ? Sim : Sre) + (size_t)(ib * 128 + n * 32 + lane) * SEQ + kh * DLT * 64;
          prefetch_l2(sp, PF_S * 128);
          const unsigned* cab = &sy->cnt[(CNT_AB + (kh * 4 + n) * 8) * 32];
          static_assert(DLT == 4, "K half 1 starts at the second pair");
          wait_count(cab + kh * 32, (ep0 + 1) * 16);
          if (lane == 0) mbar_arrive(base + BAR_DEP);
          wait_count(cab + kh * 32 + 32, (ep0 + 1) * 16);
          if (lane == 0) mbar_arrive(base + BAR_DEP + 8);
          wait_count(cab + (lane & 7) * 32, (ep0 + 1) * 16);
          __syncwarp();
          if (lane == 0) mbar_arrive(base + BAR_DEP + 40);
          if (lane == 0) prefetch_l2(w2 + (size_t)bid * 14 * DM, 14 * DM * 2);
          wait_count(&sy->cnt[(CNT_AB + ((kh ^ 1) * 4 + n) * 8 + (lane & 7)) * 32], (ep0 + 1) * 16);
          __syncwarp();
          if (lane == 0) mbar_arrive(base + BAR_DEP + 32);
          prefetch_l2((lane & 1 ? Sim : Sre + (32 - DLT) * 64) + (size_t)(ib * 128 + (kh * 4 + n) * 16 + (lane >> 1)) * SEQ, DLT * 128);
          __nanosleep(3000);
          wait_count(&sy->cnt[(CNT_H + ib * 2 + kh) * 32], (ep0 + 1) * 32);
          if (lane == 0) mbar_arrive(base + BAR_DEP + 16);
          __nanosleep(1000);
          wait_count(&sy->cnt[(CNT_H2 + ib * 2 + kh) * 32], (ep0 + 1) * 32);
          if (lane == 0) mbar_arrive(base + BAR_DEP + 24);
        } else {
          mbar_wait(base + BAR_RED + 8, 0);
          {
            float v = 0.f;
#pragma unroll
            for (int i = 0; i < 2; i++) {
              const float4 p = *(const float4*)(smem + STG_OFF + lane * 144 + i * 16);
              v += (p.x + p.y) + (p.z + p.w);
            }
            const float o = __shfl_xor_sync(0xffffffffu, v, 1);
            if (lane == 0) mbar_arrive(base + BAR_CSA);
            const float mean = v * (1.f / DM), var = fmaxf(fmaf(-mean, mean, o * (1.f / DM)), 0.f);
            const float r1 = rsqrtf(var + 1e-5f);
            const float rh = 0.25f * r1 * rsqrtf(fmaf(var * r1, r1, 1e-5f));
            if (!(lane & 1))
              st_raw4(&sy->stat[ib1 * 128 + j1 * 16 + (lane >> 1)], tagf(r1, tag), __float_as_uint(r1 * mean),
                      __float_as_uint(rh), __float_as_uint(rh * mean));
          }
          const uint32_t bb = __ldg((const uint32_t*)(b2 + ckeep) + lane);
          *(float2*)(smem + B2_OFF + lane * 8) = make_float2(0.5f * bf_lo(bb), 0.5f * bf_hi(bb));
#pragma unroll 1
          for (int ph = 0; ph < 2; ph++) {
            const int t0 = ph * (NH1 / 2) + lane, t1 = min(t0 + 32, ph ? 111 : NH1 / 2 - 1);
            const uint32_t b0 = __ldg((const uint32_t*)(b1 + j1 * 224) + t0), b1v = __ldg((const uint32_t*)(b1 + j1 * 224) + t1);
            uint2 c0 = ld_gpu2(&sy->csB[j1 * 224 + 2 * t0]), c1 = ld_gpu2(&sy->csB[j1 * 224 + 2 * t1]);
            settle2(c0, &sy->csB[j1 * 224 + 2 * t0], tag ^ 1);
            settle2(c1, &sy->csB[j1 * 224 + 2 * t1], tag ^ 1);
            *(float4*)(smem + CSB_OFF + t0 * 16) =
                make_float4(__uint_as_float(c0.x), __uint_as_float(c0.y), 0.25f * bf_lo(b0), 0.25f * bf_hi(b0));
            *(float4*)(smem + CSB_OFF + t1 * 16) =
                make_float4(__uint_as_float(c1.x), __uint_as_float(c1.y), 0.25f * bf_lo(b1v), 0.25f * bf_hi(b1v));
            __syncwarp();
            if (lane == 0) mbar_arrive(base + BAR_CSB + 8 * ph);
          }
        }
      }
    }
    __syncwarp();
  } else {
    {
      const int r0 = tid >> 3, ch = tid & 7;
      const __nv_bfloat16* xg = x + (size_t)(ib1 * 128 + r0) * DM + ch * 8;
      const __nv_bfloat16* hg = (kh1 ? Him : Hre) + (size_t)(n1 * 128 + r0) * DM + ch * 8;
      const uint32_t dst = base + r0 * 128 + ((ch ^ (r0 & 7)) << 4);
#pragma unroll
      for (int i = 0; i < 4; i++) {
        cp_async16(dst + i * 4096, xg + i * 32 * DM);
        cp_async16(dst + 8 * CELL + i * 4096, hg + i * 32 * DM);
      }
      asm volatile("cp.async.commit_group;" ::: "memory");
    }
    if (elect_one()) {
      if (warp == 0 || warp >= 5) mbar_init(base + BAR_FULL + 8 * warp, 1);
      mbar_init(base + BAR_EMPTY + 8 * warp, 16);
      asm volatile("fence.mbarrier_init.release.cluster;" ::: "memory");
    }
    __syncwarp();
    asm volatile("barrier.cluster.arrive.relaxed.aligned;" ::: "memory");
    asm volatile("setmaxnreg.inc.sync.aligned.u32 216;");
    asm volatile("bar.sync 0;" ::: "memory");
    const int wg = warp >> 2, wq = warp & 3;
    const uint32_t dbase = (base & 0x3FFFF) >> 4;
    Cons c{LBO_K + dbase + wg * 512, dbase, base, mapa(base + BAR_EMPTY, lane & 1), (uint32_t)lane};
    const uint32_t box = base + STG_OFF + warp * 2048;
    const uint32_t stg = box + (lane & 15) * 64 + (((lane >> 1) & 3) << 4);
    const int row1 = ib1 * 128 + warp * 16;
    const uint32_t q2 = (lane & 3) * 2;
    auto put = [&](auto G, auto PEND, uint32_t r0, uint32_t r1) {
      constexpr int e = decltype(G)::value / 4, gl = decltype(G)::value % 4;
      if (gl == 0 && e >= 2) {
        if (elect_one()) asm volatile("cp.async.bulk.wait_group.read %0;" ::"n"(decltype(PEND)::value) : "memory");
        __syncwarp();
      }
      stmatrix2((stg + (e & 1) * 1024) ^ (gl << 4), r0, r1);
    };
    auto store_box = [&](auto E) {
      constexpr int e = decltype(E)::value;
      fence_async_smem();
      __syncwarp();
      if (elect_one()) {
        if (e < 4) tma_store(&maps.abS, box + (e & 1) * 1024, n1 * 128 + e * 32, kh1 * SEQ + row1);
        else tma_store(&maps.hS, box + (e & 1) * 1024, j1 * 224 + (e - 4) * 32, row1);
      }
    };
    auto publish = [&](int cnt) {
      if (elect_one()) {
        asm volatile("cp.async.bulk.wait_group 0;" ::: "memory");
        red_add(&sy->cnt[cnt * 32]);
      }
    };

    float accA[64];
    uint4 hr0, hr1;
    uint32_t ep0, tag;
    static_for<0, 8>([&](auto K) {
      constexpr int k = decltype(K)::value;
      c.step<k, 128>(accA);
      if (k == 0) {
        const __nv_bfloat16* hp = (kh1 ? Him : Hre) + (size_t)(n1 * 128 + ib1 * 8 + warp) * DM + lane * 8;
        hr0 = ldg128(hp); hr1 = ldg128(hp + 256);
        ep0 = ld_relaxed(&sy->epoch[bid * 32 + lane]);
      }
      if (k == 4) {
        sts32(base + STG_OFF + 4608 + warp * 144 + lane * 4, sum8(hr0) + sum8(hr1));
        __syncwarp();
        if (lane == 0) mbar_arrive(base + BAR_RED);
      }
      if (k == XA) {
        mbar_wait(base + BAR_XALL, 0);
        const uint32_t xa = base + (lane >> 2) * CELL + (j1 * 16 + warp * 2) * 128 + (lane & 3) * 32 + ((lane >> 2) & 1) * 16;
        const uint4 p0 = lds128(xa), p1 = lds128(xa ^ 16), p2 = lds128(xa + 128), p3 = lds128((xa + 128) ^ 16);
        const float s0 = sum8(p0) + sum8(p1), z0 = sq8(p0) + sq8(p1), s1 = sum8(p2) + sum8(p3), z1 = sq8(p2) + sq8(p3);
        const bool hi = lane & 16, od = lane & 8;
        float a = (hi ? s1 : s0) + __shfl_xor_sync(0xffffffffu, hi ? s0 : s1, 16);
        const float b = (hi ? z1 : z0) + __shfl_xor_sync(0xffffffffu, hi ? z0 : z1, 16);
        a = (od ? b : a) + __shfl_xor_sync(0xffffffffu, od ? a : b, 8);
        sts32(base + STG_OFF + (warp * 4 + (lane >> 3)) * 144 + (lane & 7) * 4, a);
        __syncwarp();
        if (lane == 0) mbar_arrive(base + BAR_RED + 8);
      }
      if (k == 7) asm volatile("{\n.reg .b32 t;\nnot.b32 t, %1;\nand.b32 %0, t, 1;\n}" : "=r"(tag) : "r"(ep0) : "memory");
    });
    float accH1[NH1 / 2];
    uint4 st[2];
    const uint4* stp = &sy->stat[ib1 * 128 + wg * 64 + wq * 16 + (lane >> 2)];
    float ra0, ma0, ra1, ma1, rh0, mh0, rh1, mh1;
    float2 ca[16] = {};
    auto epi_a = [&](auto K) {
      constexpr int k = decltype(K)::value;
      constexpr int g0 = ea_end(k - 1), g1 = ea_end(k);
      if (k == EA_BLOCKS - 1) publish(CNT_AB + j1 * 8 + u);
      static_for<g0, g1>([&](auto G) {
        constexpr int g = decltype(G)::value;
        const float2 cs = ca[g];
        put(G, std::integral_constant<int, g == g0 ? 1 : 0>{}, pack_bf16(fmaf(accA[4 * g], ra0, cs.x * ma0), fmaf(accA[4 * g + 1], ra0, cs.y * ma0)),
            pack_bf16(fmaf(accA[4 * g + 2], ra1, cs.x * ma1), fmaf(accA[4 * g + 3], ra1, cs.y * ma1)));
      });
      static_for<g1, ea_end(k + 1)>([&](auto G) {
        constexpr int g = decltype(G)::value;
        ca[g] = lds64f(base + CSA_OFF + (g * 8 + q2) * 4);
      });
    };
    static_for<0, 8>([&](auto K) {
      constexpr int k = decltype(K)::value;
      c.step<Q_H1 + k, NH1>(accH1);
      static_for<ea_end(k - 2) / 4, ea_end(k - 1) / 4>(store_box);
      if (k == EA_START - 3) { st[0] = ld_gpu4(stp); st[1] = ld_gpu4(stp + 8); }
      if (k == EA_START - 2) mbar_wait(base + BAR_CSA, 0);
      if (k == EA_START - 1) {
        pin<0, 64>(accA);
        settle<2>(st, stp, tag ^ 1);
        const float sg = kh1 ? -1.f : 1.f;
        ra0 = sg * __uint_as_float(st[0].x); ma0 = -sg * __uint_as_float(st[0].y);
        ra1 = sg * __uint_as_float(st[1].x); ma1 = -sg * __uint_as_float(st[1].y);
        rh0 = __uint_as_float(st[0].z); mh0 = -__uint_as_float(st[0].w);
        rh1 = __uint_as_float(st[1].z); mh1 = -__uint_as_float(st[1].w);
      }
      epi_a(K);
    });
    float accH2[NH2 / 2], accS[64], th[GV_RATE];
    float4 cb[28];
    auto hval = [&](auto V) -> float& {
      constexpr int v = decltype(V)::value;
      if constexpr (v < NH1 / 2) return accH1[v]; else return accH2[v - NH1 / 2];
    };
    static_for<0, GV_BLOCKS>([&](auto K) {
      constexpr int k = decltype(K)::value;
      if constexpr (k < 8) c.step<Q_H2 + k, NH2>(accH2); else c.step<Q_H2 + k, 128>(accS);
      static_for<ea_end(6 + k) / 4, ea_end(7 + k) / 4>(store_box);
      static_for<4 + gv_end(k - 3) / 16, 4 + gv_end(k - 2) / 16>(store_box);
      if (k == 0) pin<0, NH1 / 2>(accH1);
      if constexpr (8 + k < EA_BLOCKS) epi_a(std::integral_constant<int, 8 + k>{});
      if (k == GV_START - 1) mbar_wait(base + BAR_CSB, 0);
      if (gv_end(k) <= NH1 / 2 && gv_end(k + 1) > NH1 / 2) mbar_wait(base + BAR_CSB + 8, 0);
      if (k == 8) pin<0, NH2 / 2>(accH2);
      constexpr int v0 = gv_end(k - 2), v1 = gv_end(k - 1), v2 = gv_end(k), v3 = gv_end(k + 1);
      if (gv_end(k - 3) >= 80 && gv_end(k - 4) < 80) publish(CNT_H + ib1 * 2 + kh1);
      if (k == GV_BLOCKS - 1) {
        publish(CNT_H2 + ib1 * 2 + kh1);
        if (elect_one()) mbar_arrive(base + BAR_STG);
      }
      static_for<v0, v1>([&](auto V) {
        constexpr int v = decltype(V)::value;
        hval(V) = fmaf(hval(V), th[v - v0], hval(V));
      });
      static_for<v0 / 4, v1 / 4>([&](auto G) {
        constexpr int g = decltype(G)::value;
        using std::integral_constant;
        put(integral_constant<int, 16 + g>{}, integral_constant<int, g == v0 / 4 ? 1 : 0>{},
            pack_bf16(hval(integral_constant<int, 4 * g>{}), hval(integral_constant<int, 4 * g + 1>{})),
            pack_bf16(hval(integral_constant<int, 4 * g + 2>{}), hval(integral_constant<int, 4 * g + 3>{})));
      });
      static_for<(v2 + 3) / 4, (v3 + 3) / 4>([&](auto G) {
        constexpr int g = decltype(G)::value;
        cb[g] = lds128f(base + CSB_OFF + (g * 4 + (lane & 3)) * 16);
      });
      static_for<v1, v2>([&](auto V) {
        constexpr int v = decltype(V)::value, g = v / 4;
        const float cs = (v & 1) ? cb[g].y : cb[g].x, bb = (v & 1) ? cb[g].w : cb[g].z;
        const float hp = (v & 2) ? fmaf(hval(V), rh1, fmaf(cs, mh1, bb)) : fmaf(hval(V), rh0, fmaf(cs, mh0, bb));
        hval(V) = hp;
        th[v - v1] = tanh_fast(hp * fmaf(hp * hp, 64.f * 0.0356774081363f, 4.f * 0.7978845608029f));
      });
    });
    c.run<Q_H2 + GV_BLOCKS, Q_M - 2>(accS);
    float accM[64];
    c.step<Q_M - 2, 128>(accS);
#pragma unroll
    for (int g = 0; g < 8; g++) {
      const float2 bb = lds64f(base + B2_OFF + (g * 8 + q2) * 4);
      accM[4 * g] = accM[4 * g + 2] = bb.x;
      accM[4 * g + 1] = accM[4 * g + 3] = bb.y;
    }
    pin<0, 32>(accM);
    c.step<Q_M - 1, 128>(accS);
#pragma unroll
    for (int g = 32; g < 64; g++) accM[g] = 0.f;
    pin<32, 64>(accM);
    uint4 pp[4];
    uint32_t xr[16];
    const int xrow = wg * 64 + wq * 16 + (lane & 15);
    const uint32_t xs = base + STG_OFF + xrow * 128 + (((lane >> 4) ^ (xrow & 7)) << 4);
    uint4* mine = part + bid * 2048 + warp * 128 + lane;
    const uint4* theirs = part + (bid ^ 64) * 2048 + warp * 128 + lane;
    auto send = [&](int slot, const float* v) {
      st_raw4(mine + (slot >> 2) * 1024 + (slot & 3) * 32, (pack_bf16(v[0], v[1]) & ~1u) | tag, pack_bf16(v[2], v[3]), pack_bf16(v[4], v[5]),
              pack_bf16(v[6], v[7]));
    };
    static_for<0, 4>([&](auto K) {
      constexpr int k = decltype(K)::value;
      c.step<Q_M + k, 128>(accM);
      if (k == 0) pin<0, 64>(accS);
      send(k, &accS[32 + 8 * k]);
    });
    c.run<Q_M + 4, Q_HALF - 8>(accM);
    static_for<0, 8>([&](auto K) {
      constexpr int k = decltype(K)::value;
      c.step<Q_HALF - 8 + k, 128>(accM);
      if (k == 0) {
        mbar_wait(base + BAR_X, 0);
#pragma unroll
        for (int g = 0; g < 8; g += 2) ldmatrix4(xs ^ (g << 4), &xr[2 * g]);
      }
      if (k < 4) pp[k] = ld_gpu4(theirs + k * 32);
      if (k == 5) settle<4>(pp, theirs, tag ^ 1);
      if (k == 5 || k == 6) {
#pragma unroll
        for (int t = 2 * (k - 5); t < 2 * (k - 4); t++) {
          const uint32_t w[4] = {pp[t].x, pp[t].y, pp[t].z, pp[t].w};
#pragma unroll
          for (int v = 0; v < 4; v++) { accS[8 * t + 2 * v] += bf_lo(w[v]); accS[8 * t + 2 * v + 1] += bf_hi(w[v]); }
        }
        pin<16 * (k - 5), 16 * (k - 4)>(accS);
      }
    });
    static_for<0, 2 * DLT>([&](auto K) {
      constexpr int k = decltype(K)::value;
      c.step<Q_HALF + k, 64>(accS);
      if (k == 0) {
        pin<0, 64>(accM);
#pragma unroll
        for (int t = 0; t < 4; t++) send(4 + t, &accM[32 + 8 * t]);
      }
      if (k == 2 * DLT - 1) {
#pragma unroll
        for (int t = 0; t < 4; t++) pp[t] = ld_gpu4(theirs + 1024 + t * 32);
      }
    });
    if (lane == 0) mbar_arrive_cluster(mapa(base + BAR_PEER, rank ^ 1));
    settle<4>(pp, theirs + 1024, tag ^ 1);
    wg_wait<0>();
    pin<0, 32>(accS);
#pragma unroll
    for (int t = 0; t < 4; t++) {
      const uint32_t w[4] = {pp[t].x, pp[t].y, pp[t].z, pp[t].w};
      uint32_t o[4];
#pragma unroll
      for (int v = 0; v < 4; v++) {
        const int i = 8 * t + 2 * v;
        o[v] = add_bf16x2(pack_bf16(accS[i] * silu_half(bf_lo(w[v]) + accM[i]), accS[i + 1] * silu_half(bf_hi(w[v]) + accM[i + 1])),
                          xr[4 * t + v]);
      }
      stmatrix4(xs ^ (t << 5), o[0], o[1], o[2], o[3]);
      if (t & 1) {
        __syncwarp();
#pragma unroll
        for (int i = 0; i < 2; i++) {
          const int r = wg * 64 + wq * 16 + i * 8 + (lane >> 2), ch = (t >> 1) * 4 + (lane & 3);
          const uint4 v = lds128(base + STG_OFF + r * 128 + (((ch ^ r) & 7) << 4));
          *(uint4*)(out + (size_t)(ib * 128 + r) * DM + ckeep + ch * 8) = v;
        }
      }
    }
    if (warp == 0) sy->epoch[bid * 32 + lane] = ep0 + 1;
  }
}

typedef CUresult (*EncodeFn)(CUtensorMap*, CUtensorMapDataType, cuuint32_t, void*, const cuuint64_t*, const cuuint64_t*,
                             const cuuint32_t*, const cuuint32_t*, CUtensorMapInterleave, CUtensorMapSwizzle,
                             CUtensorMapL2promotion, CUtensorMapFloatOOBfill);

void make_map(EncodeFn fn, CUtensorMap* m, const void* ptr, uint64_t rows, uint64_t cols, uint32_t brows, uint32_t bcols,
              CUtensorMapSwizzle sw) {
  cuuint64_t gd[2] = {cols, rows};
  cuuint64_t gs[1] = {cols * 2};
  cuuint32_t bd[2] = {bcols, brows};
  cuuint32_t es[2] = {1, 1};
  fn(m, CU_TENSOR_MAP_DATA_TYPE_BFLOAT16, 2, const_cast<void*>(ptr), gd, gs, bd, es, CU_TENSOR_MAP_INTERLEAVE_NONE, sw,
     CU_TENSOR_MAP_L2_PROMOTION_L2_128B, CU_TENSOR_MAP_FLOAT_OOB_FILL_NONE);
}

}

extern "C" void kernel_launch(void* const* d_in, const int* in_sizes, int n_in, void* d_out, int out_size) {
  (void)in_sizes; (void)n_in; (void)out_size;
  const __nv_bfloat16* x = (const __nv_bfloat16*)d_in[0];
  const __nv_bfloat16* Sre = (const __nv_bfloat16*)d_in[1];
  const __nv_bfloat16* Sim = (const __nv_bfloat16*)d_in[2];
  const __nv_bfloat16* Hre = (const __nv_bfloat16*)d_in[3];
  const __nv_bfloat16* Him = (const __nv_bfloat16*)d_in[4];
  const __nv_bfloat16* w1 = (const __nv_bfloat16*)d_in[6];
  const __nv_bfloat16* b1 = (const __nv_bfloat16*)d_in[7];
  const __nv_bfloat16* w2 = (const __nv_bfloat16*)d_in[8];
  const __nv_bfloat16* b2 = (const __nv_bfloat16*)d_in[9];

  void* fnp = nullptr;
  cudaDriverEntryPointQueryResult qr;
  cudaGetDriverEntryPoint("cuTensorMapEncodeTiled", &fnp, cudaEnableDefault, &qr);
  EncodeFn fn = (EncodeFn)fnp;
  void *ab = nullptr, *h = nullptr, *sy = nullptr, *part = nullptr;
  cudaGetSymbolAddress(&ab, g_ab);
  cudaGetSymbolAddress(&h, g_h);
  cudaGetSymbolAddress(&sy, g_sync);
  cudaGetSymbolAddress(&part, g_part);
  Maps maps;
  const CUtensorMapSwizzle S128 = CU_TENSOR_MAP_SWIZZLE_128B, S64 = CU_TENSOR_MAP_SWIZZLE_64B;
  make_map(fn, &maps.x, x, SEQ, DM, 128, 64, S128);
  make_map(fn, &maps.H[0], Hre, DM, DM, 64, 64, S128);
  make_map(fn, &maps.H[1], Him, DM, DM, 64, 64, S128);
  make_map(fn, &maps.w1, w1, DM, FF, 64, 64, S128);
  make_map(fn, &maps.S[0], Sre, SEQ, SEQ, 64, 64, S128);
  make_map(fn, &maps.S[1], Sim, SEQ, SEQ, 64, 64, S128);
  make_map(fn, &maps.abL, ab, 2 * SEQ, DM, 64, 64, S128);
  make_map(fn, &maps.hL, h, SEQ, FF, 64, 64, S128);
  make_map(fn, &maps.w2, w2, FF, DM, 64, 64, S128);
  make_map(fn, &maps.abS, ab, 2 * SEQ, DM, 16, 32, S64);
  make_map(fn, &maps.hS, h, SEQ, FF, 16, 32, S64);
  int dev = 0, sms = 0, clusters = 0;
  cudaGetDevice(&dev);
  cudaDeviceGetAttribute(&sms, cudaDevAttrMultiProcessorCount, dev);
  cudaFuncSetAttribute(fused_kernel<true>, cudaFuncAttributeMaxDynamicSharedMemorySize, SMEM_BYTES);
  cudaFuncSetAttribute(fused_kernel<false>, cudaFuncAttributeMaxDynamicSharedMemorySize, SMEM_BYTES);
  cudaLaunchConfig_t cfg = {};
  cfg.gridDim = dim3(NCTA + 4);
  cfg.blockDim = dim3(384);
  cfg.dynamicSmemBytes = SMEM_BYTES;
  cudaLaunchAttribute attr;
  attr.id = cudaLaunchAttributeClusterDimension;
  attr.val.clusterDim.x = 2; attr.val.clusterDim.y = 1; attr.val.clusterDim.z = 1;
  cfg.attrs = &attr;
  cfg.numAttrs = 1;
  if (cudaOccupancyMaxActiveClusters(&clusters, fused_kernel<true>, &cfg) != cudaSuccess) { clusters = 0; (void)cudaGetLastError(); }
  auto kernel = sms == NCTA + 4 && clusters == NCTA / 2 + 2 ? fused_kernel<true> : fused_kernel<false>;
  kernel<<<NCTA + 4, 384, SMEM_BYTES>>>(x, Hre, Him, (Sync*)sy, w1, b1, b2, w2, Sre, Sim, (uint4*)part, (__nv_bfloat16*)d_out, maps);
}
```
